```python
import torch

def _softmax(x, axis=-1):
    return torch.softmax(x, dim=axis)
def _gelu(x):
    return torch.nn.functional.gelu(x, approximate="tanh")
def _silu(x):
    return torch.nn.functional.silu(x)
def _sigmoid(x):
    return torch.sigmoid(x)
def _layernorm(x, axis=-1, eps=1e-5):
    m = x.mean(dim=axis, keepdim=True)
    v = x.var(dim=axis, keepdim=True, unbiased=False)
    return (x - m) / torch.sqrt(v + eps)
def _scatter_add(tgt, idx, src, axis=0):
    return tgt.clone().index_add_(axis, idx, src)
def _segment_sum(src, seg, n):
    out = torch.zeros((n,) + src.shape[1:], dtype=src.dtype)
    return out.index_add_(0, seg, src)
def _pad(x, pw):
    flat = tuple(v for pair in reversed(pw) for v in pair)
    return torch.nn.functional.pad(x, flat)

kernel_name = 'parallel_sum__sliding_local_dilated__dense_activation_squared_relu__prompt'

def setup_inputs():

    _w = (lambda a: (lambda t: t.to(torch.bfloat16) if t.is_floating_point() else t)(torch.as_tensor(a)))
    def _A_setup():
        B, S, D = 1, 2048, 576
        return {
            "x": _w((lambda *s: torch.randn(*s, dtype=torch.bfloat16) * 0.05)(B, S, D)),
            "wqkv": _w((lambda *s: torch.randn(*s, dtype=torch.bfloat16) * 0.1)(D, 3 * D)),
            "wo": _w((lambda *s: torch.randn(*s, dtype=torch.bfloat16) * 0.05)(D, D)),
        }
    _A_in = _A_setup()

    def _B_setup():
        B, S, D, F = 1, 2048, 576, 4608
        return {
            "x": _w((lambda *s: torch.randn(*s, dtype=torch.bfloat16) * 0.05)(B, S, D)),
            "w1": _w((lambda *s: torch.randn(*s, dtype=torch.bfloat16) * 0.05)(D, F)),
            "b1": _w((lambda *s: torch.randn(*s, dtype=torch.bfloat16) * 0.2)(F)),
            "w2": _w((lambda *s: torch.randn(*s, dtype=torch.bfloat16) * 0.05)(F, D)),
            "b2": _w((lambda *s: torch.randn(*s, dtype=torch.bfloat16) * 1.6)(D)),
        }
    _B_in = _B_setup()

    return {
        "A_x": _A_in["x"],
        "A_wqkv": _A_in["wqkv"],
        "A_wo": _A_in["wo"],
        "B_x": _B_in["x"],
        "B_w1": _B_in["w1"],
        "B_b1": _B_in["b1"],
        "B_w2": _B_in["w2"],
        "B_b2": _B_in["b2"],
    }

def reference(A_x, A_wqkv, A_wo, B_x, B_w1, B_b1, B_w2, B_b2):
    def _A_ref(x, wqkv, wo):
        B, S, D = x.shape
        H = 32; Dh = D // H
        W, dil = 8, 2
        qkv = (lambda x, *d: x.permute(*d))((x @ wqkv).reshape(B, S, 3, H, Dh), 2, 0, 3, 1, 4)
        q, k, v = qkv[0], qkv[1], qkv[2]
        scale = Dh ** -0.5
        pos = torch.arange(S)
        off = torch.arange(W) * dil
        idx = pos[:, None] - off[None, :]
        mask = idx >= 0
        idx_c = torch.where(mask, idx, 0).reshape(-1)
        kg = k[:, :, idx_c, :].reshape(B, H, S, W, Dh)
        vg = v[:, :, idx_c, :].reshape(B, H, S, W, Dh)
        logits = torch.einsum("bhsd,bhswd->bhsw", q, kg) * scale
        logits = torch.where(mask[None, None, :, :], logits, -1e9)
        attn = _softmax(logits, axis=-1)
        o = torch.einsum("bhsw,bhswd->bhsd", attn, vg)
        return (lambda x, *d: x.permute(*d))(o, 0, 2, 1, 3).reshape(B, S, D) @ wo

    def _B_ref(x, w1, b1, w2, b2):
        h = torch.einsum("bsd,df->bsf", x, w1) + b1
        zero = torch.zeros_like(h)
        r = torch.where(h > zero, h, zero)
        h = r * r
        out = torch.einsum("bsf,fd->bsd", h, w2) + b2
        return out

    x = A_x
    xn = _layernorm(x, axis=-1)
    return x + _A_ref(xn, A_wqkv, A_wo) + _B_ref(xn, B_w1, B_b1, B_w2, B_b2)
```

```cpp
#include <cuda_runtime.h>
#include <cuda_bf16.h>
#include <cuda.h>
#include <stdint.h>

#define CONS_REGS 240
#define HELP_REGS 24
#define AT_S 4
#define AT_O 8
#define P2_LD 12
#define P2_LW 20
#define P2_REL 32
#define P2_GIVE 39

namespace {

constexpr int kS = 2048, kD = 576, kF = 4608, kQKV = 1728;
constexpr int XN_BYTES = 9 * 16384;
constexpr int SLOT = 24576;
constexpr int OFF_RING = XN_BYTES;
constexpr int OFF_MISC = XN_BYTES + 3 * SLOT;
constexpr int OFF_WO = 3 * SLOT;
constexpr int OFF_STG = OFF_RING;
constexpr int OFF_BIAS = OFF_MISC + 512;
constexpr int OFF_EPOCH = OFF_MISC + 368;
constexpr int OFF_B2 = OFF_BIAS + 1152;
constexpr int SMEM_BYTES = OFF_B2 + 384 + 1024;

constexpr int OFF_S8 = 94208;
constexpr int OFF_O = 114688;
constexpr int OFF_XT = 131072;

constexpr int B_FULL1 = 0;
constexpr int B_FULL2 = 24;
constexpr int B_BIAS = 40;
constexpr int B_EMPTY1 = 48;
constexpr int B_EMPTY2 = 72;
constexpr int B_XDONE = 104;
constexpr int B_PART = 112;
constexpr int N_BAR = 15;

constexpr int SC_SYNC = 0;
constexpr int SC_LL = 32;
constexpr int SC_PART = SC_LL + 16 * 1536;
constexpr int SC_OF = SC_PART + 8 * 1024;
constexpr int SC_HALO = SC_OF + 8 * 1280;
constexpr int SC_SIZE = SC_HALO + 8 * 1536;
__device__ uint4 g_scr[16 * SC_SIZE];
#define PROF(i)
#define PROFW(i)
#define TL(n)

__device__ __forceinline__ uint32_t smem_u32(const void* p) { return (uint32_t)__cvta_generic_to_shared(p); }
__device__ __forceinline__ void mbar_init(uint32_t bar, uint32_t cnt) {
  asm volatile("mbarrier.init.shared::cta.b64 [%0], %1;" ::"r"(bar), "r"(cnt) : "memory");
}
__device__ __forceinline__ void mbar_expect_tx(uint32_t bar, uint32_t bytes) {
  asm volatile("mbarrier.arrive.expect_tx.shared::cta.b64 _, [%0], %1;" ::"r"(bar), "r"(bytes) : "memory");
}
__device__ __forceinline__ void mbar_arrive(uint32_t bar) {
  asm volatile("mbarrier.arrive.shared::cta.b64 _, [%0];" ::"r"(bar) : "memory");
}
__device__ __forceinline__ void release_pair(uint32_t addr, bool on) {
  if (on && addr < (2u << 24)) asm volatile("mbarrier.arrive.relaxed.cluster.shared::cluster.b64 _, [%0];" ::"r"(addr) : "memory");
}
__device__ __forceinline__ bool mbar_try_wait(uint32_t bar, uint32_t parity) {
  uint32_t ok;
  asm volatile("{\n.reg .pred p;\nmbarrier.try_wait.parity.shared::cta.b64 p, [%1], %2;\nselp.u32 %0, 1, 0, p;\n}\n"
               : "=r"(ok) : "r"(bar), "r"(parity) : "memory");
  return ok;
}
__device__ __forceinline__ bool mbar_test_wait(uint32_t bar, uint32_t parity) {
  uint32_t ok;
  asm volatile("{\n.reg .pred p;\nmbarrier.test_wait.parity.shared::cta.b64 p, [%1], %2;\nselp.u32 %0, 1, 0, p;\n}\n"
               : "=r"(ok) : "r"(bar), "r"(parity) : "memory");
  return ok;
}
__device__ __forceinline__ void mbar_wait(uint32_t bar, uint32_t parity) {
  asm volatile("{\n.reg .pred p, q;\n.reg .u32 n;\nmov.u32 n, 0;\n"
               "WAIT_LOOP:\n.pragma \"nounroll\";\nmbarrier.try_wait.parity.shared::cta.b64 p, [%0], %1;\n@p bra WAIT_DONE;\nadd.u32 n, n, 1;\n"
               "setp.lt.u32 q, n, 0x40000;\n@q bra WAIT_LOOP;\nWAIT_DONE:\n}\n" ::"r"(bar), "r"(parity) : "memory");
}
__device__ __forceinline__ void mbar_wait_async(uint32_t bar, uint32_t parity) {
  if (!mbar_try_wait(bar, parity)) mbar_wait(bar, parity);
}
__device__ __forceinline__ unsigned ld_acquire(const unsigned* p) {
  unsigned v;
  asm volatile("ld.acquire.gpu.global.u32 %0, [%1];" : "=r"(v) : "l"(p) : "memory");
  return v;
}
__device__ __forceinline__ void poll_ge(const unsigned* p, unsigned target) {
#pragma unroll 1
  for (int it = 0; it < (1 << 16) && (int)(ld_acquire(p) - target) < 0; it++) __nanosleep(200);
}
__device__ __forceinline__ void tma_load_2d(uint32_t dst, const CUtensorMap* tm, int c0, int c1, uint32_t bar) {
  asm volatile("cp.async.bulk.tensor.2d.shared::cluster.global.mbarrier::complete_tx::bytes [%0], [%1, {%3, %4}], [%2];"
               ::"r"(dst), "l"(tm), "r"(bar), "r"(c0), "r"(c1) : "memory");
}
__device__ __forceinline__ void tma_mc_2d(uint32_t dst, const CUtensorMap* tm, int c0, int c1, uint32_t bar) {
  asm volatile("cp.async.bulk.tensor.2d.shared::cluster.global.mbarrier::complete_tx::bytes.multicast::cluster [%0], [%1, {%3, %4}], [%2], %5;"
               ::"r"(dst), "l"(tm), "r"(bar), "r"(c0), "r"(c1), "h"((uint16_t)3) : "memory");
}
__device__ __forceinline__ void prefetch_tmap(const CUtensorMap* tm) {
  asm volatile("prefetch.tensormap [%0];" ::"l"(tm) : "memory");
}
__device__ __forceinline__ void l2_prefetch(const void* p, uint32_t bytes) {
  asm volatile("cp.async.bulk.prefetch.L2.global [%0], %1;" ::"l"(p), "r"(bytes) : "memory");
}
__device__ __forceinline__ void wgmma_fence() { asm volatile("wgmma.fence.sync.aligned;" ::: "memory"); }
__device__ __forceinline__ void wgmma_commit() { asm volatile("wgmma.commit_group.sync.aligned;" ::: "memory"); }
template <int N>
__device__ __forceinline__ void wgmma_wait() { asm volatile("wgmma.wait_group.sync.aligned %0;" ::"n"(N) : "memory"); }
__host__ __device__ constexpr uint32_t make_desc(uint32_t addr, uint32_t lbo) { return ((addr & 0x3FFFF) >> 4) | ((lbo >> 4) << 16); }
__device__ __forceinline__ void bar_sync(int id, int n) { asm volatile("bar.sync %0, %1;" ::"r"(id), "r"(n) : "memory"); }
__device__ __forceinline__ void bar_arrive(int id, int n) { asm volatile("bar.arrive %0, %1;" ::"r"(id), "r"(n) : "memory"); }
__device__ __forceinline__ void ldsm_x4(uint32_t (&r)[4], uint32_t addr) {
  asm volatile("ldmatrix.sync.aligned.m8n8.x4.shared.b16 {%0, %1, %2, %3}, [%4];"
               : "=r"(r[0]), "=r"(r[1]), "=r"(r[2]), "=r"(r[3]) : "r"(addr) : "memory");
}
__device__ __forceinline__ void stsm_x4(uint32_t addr, uint32_t r0, uint32_t r1, uint32_t r2, uint32_t r3) {
  asm volatile("stmatrix.sync.aligned.m8n8.x4.shared.b16 [%0], {%1, %2, %3, %4};"
               ::"r"(addr), "r"(r0), "r"(r1), "r"(r2), "r"(r3) : "memory");
}
__device__ __forceinline__ uint32_t pack_bf16(float lo, float hi) {
  uint32_t r;
  asm("cvt.rn.bf16x2.f32 %0, %1, %2;" : "=r"(r) : "f"(hi), "f"(lo));
  return r;
}
__device__ __forceinline__ uint32_t fma2(uint32_t a, uint32_t b, uint32_t c) {
  uint32_t r;
  asm("fma.rn.bf16x2 %0, %1, %2, %3;" : "=r"(r) : "r"(a), "r"(b), "r"(c));
  return r;
}
__device__ __forceinline__ float bf_lo(uint32_t v) { return __uint_as_float(v << 16); }
__device__ __forceinline__ float bf_hi(uint32_t v) { return __uint_as_float(v & 0xffff0000u); }
template <int N>
__device__ __forceinline__ void fence_regs(float (&a)[N]) {
#pragma unroll
  for (int i = 0; i < N; i++) asm volatile("" : "+f"(a[i])::"memory");
}
__device__ __forceinline__ void st_b128(uint4* p, uint32_t a, uint32_t b, uint32_t c, uint32_t d) {
  asm volatile("{\n.reg .b128 t;\n.reg .b64 lo, hi;\nmov.b64 lo, {%1, %2};\nmov.b64 hi, {%3, %4};\nmov.b128 t, {lo, hi};\n"
               "st.relaxed.gpu.global.b128 [%0], t;\n}\n" ::"l"(p), "r"(a), "r"(b), "r"(c), "r"(d) : "memory");
}
__device__ __forceinline__ uint4 ld_b128(const uint4* p) {
  uint4 v;
  asm volatile("{\n.reg .b128 t;\n.reg .b64 lo, hi;\nld.relaxed.gpu.global.b128 t, [%4];\nmov.b128 {lo, hi}, t;\n"
               "mov.b64 {%0, %1}, lo;\nmov.b64 {%2, %3}, hi;\n}\n"
               : "=r"(v.x), "=r"(v.y), "=r"(v.z), "=r"(v.w) : "l"(p) : "memory");
  return v;
}
__device__ __forceinline__ uint4 ld_b128_if(const uint4* p, bool pred) {
  uint4 v;
  asm volatile("{\n.reg .b128 t;\n.reg .b64 lo, hi;\n.reg .pred q;\nsetp.ne.u32 q, %5, 0;\nmov.b64 lo, 0;\nmov.b128 t, {lo, lo};\n@q ld.relaxed.gpu.global.b128 t, [%4];\n"
               "mov.b128 {lo, hi}, t;\nmov.b64 {%0, %1}, lo;\nmov.b64 {%2, %3}, hi;\n}\n"
               : "=r"(v.x), "=r"(v.y), "=r"(v.z), "=r"(v.w) : "l"(p), "r"((uint32_t)pred) : "memory");
  return v;
}
__device__ __forceinline__ bool elect_one() {
  uint32_t p;
  asm volatile("{\n.reg .pred P;\nelect.sync _|P, 0xffffffff;\nselp.u32 %0, 1, 0, P;\n}\n" : "=r"(p));
  return p;
}
__device__ __forceinline__ void fence_gpu() { asm volatile("fence.acq_rel.gpu;" ::: "memory"); }

__device__ __forceinline__ void wgmma_ss_n192(float (&d)[96], uint32_t da, uint32_t db, int scale_d) {
  asm volatile("{\n.reg .pred p;\n.reg .b64 da, db;\nsetp.ne.b32 p, %98, 0;\nmov.b64 da, {%96, 0x40000040};\nmov.b64 db, {%97, 0x40000040};\n"
    "wgmma.mma_async.sync.aligned.m64n192k16.f32.bf16.bf16 {%0, %1, %2, %3, %4, %5, %6, %7, %8, %9, %10, %11, %12, %13, %14, %15, %16, %17, %18, %19, %20, %21, %22, %23, %24, %25, %26, %27, %28, %29, %30, %31, %32, %33, %34, %35, %36, %37, %38, %39, %40, %41, %42, %43, %44, %45, %46, %47, %48, %49, %50, %51, %52, %53, %54, %55, %56, %57, %58, %59, %60, %61, %62, %63, %64, %65, %66, %67, %68, %69, %70, %71, %72, %73, %74, %75, %76, %77, %78, %79, %80, %81, %82, %83, %84, %85, %86, %87, %88, %89, %90, %91, %92, %93, %94, %95}, da, db, p, 1, 1, 0, 1;\n}\n"
    : "+f"(d[0]), "+f"(d[1]), "+f"(d[2]), "+f"(d[3]), "+f"(d[4]), "+f"(d[5]), "+f"(d[6]), "+f"(d[7]), "+f"(d[8]), "+f"(d[9]), "+f"(d[10]), "+f"(d[11]), "+f"(d[12]), "+f"(d[13]), "+f"(d[14]), "+f"(d[15]), "+f"(d[16]), "+f"(d[17]), "+f"(d[18]), "+f"(d[19]), "+f"(d[20]), "+f"(d[21]), "+f"(d[22]), "+f"(d[23]), "+f"(d[24]), "+f"(d[25]), "+f"(d[26]), "+f"(d[27]), "+f"(d[28]), "+f"(d[29]), "+f"(d[30]), "+f"(d[31]), "+f"(d[32]), "+f"(d[33]), "+f"(d[34]), "+f"(d[35]), "+f"(d[36]), "+f"(d[37]), "+f"(d[38]), "+f"(d[39]), "+f"(d[40]), "+f"(d[41]), "+f"(d[42]), "+f"(d[43]), "+f"(d[44]), "+f"(d[45]), "+f"(d[46]), "+f"(d[47]), "+f"(d[48]), "+f"(d[49]), "+f"(d[50]), "+f"(d[51]), "+f"(d[52]), "+f"(d[53]), "+f"(d[54]), "+f"(d[55]), "+f"(d[56]), "+f"(d[57]), "+f"(d[58]), "+f"(d[59]), "+f"(d[60]), "+f"(d[61]), "+f"(d[62]), "+f"(d[63]), "+f"(d[64]), "+f"(d[65]), "+f"(d[66]), "+f"(d[67]), "+f"(d[68]), "+f"(d[69]), "+f"(d[70]), "+f"(d[71]), "+f"(d[72]), "+f"(d[73]), "+f"(d[74]), "+f"(d[75]), "+f"(d[76]), "+f"(d[77]), "+f"(d[78]), "+f"(d[79]), "+f"(d[80]), "+f"(d[81]), "+f"(d[82]), "+f"(d[83]), "+f"(d[84]), "+f"(d[85]), "+f"(d[86]), "+f"(d[87]), "+f"(d[88]), "+f"(d[89]), "+f"(d[90]), "+f"(d[91]), "+f"(d[92]), "+f"(d[93]), "+f"(d[94]), "+f"(d[95])
    : "r"(da), "r"(db), "r"(scale_d));
}
__device__ __forceinline__ void wgmma_ss0_n192(float (&d)[96], uint32_t da, uint32_t db) {
  asm volatile("{\n.reg .pred p;\n.reg .b64 da, db;\nsetp.ne.b32 p, 0, 0;\nmov.b64 da, {%96, 0x40000040};\nmov.b64 db, {%97, 0x40000040};\n"
    "wgmma.mma_async.sync.aligned.m64n192k16.f32.bf16.bf16 {%0, %1, %2, %3, %4, %5, %6, %7, %8, %9, %10, %11, %12, %13, %14, %15, %16, %17, %18, %19, %20, %21, %22, %23, %24, %25, %26, %27, %28, %29, %30, %31, %32, %33, %34, %35, %36, %37, %38, %39, %40, %41, %42, %43, %44, %45, %46, %47, %48, %49, %50, %51, %52, %53, %54, %55, %56, %57, %58, %59, %60, %61, %62, %63, %64, %65, %66, %67, %68, %69, %70, %71, %72, %73, %74, %75, %76, %77, %78, %79, %80, %81, %82, %83, %84, %85, %86, %87, %88, %89, %90, %91, %92, %93, %94, %95}, da, db, p, 1, 1, 0, 1;\n}\n"
    : "=f"(d[0]), "=f"(d[1]), "=f"(d[2]), "=f"(d[3]), "=f"(d[4]), "=f"(d[5]), "=f"(d[6]), "=f"(d[7]), "=f"(d[8]), "=f"(d[9]), "=f"(d[10]), "=f"(d[11]), "=f"(d[12]), "=f"(d[13]), "=f"(d[14]), "=f"(d[15]), "=f"(d[16]), "=f"(d[17]), "=f"(d[18]), "=f"(d[19]), "=f"(d[20]), "=f"(d[21]), "=f"(d[22]), "=f"(d[23]), "=f"(d[24]), "=f"(d[25]), "=f"(d[26]), "=f"(d[27]), "=f"(d[28]), "=f"(d[29]), "=f"(d[30]), "=f"(d[31]), "=f"(d[32]), "=f"(d[33]), "=f"(d[34]), "=f"(d[35]), "=f"(d[36]), "=f"(d[37]), "=f"(d[38]), "=f"(d[39]), "=f"(d[40]), "=f"(d[41]), "=f"(d[42]), "=f"(d[43]), "=f"(d[44]), "=f"(d[45]), "=f"(d[46]), "=f"(d[47]), "=f"(d[48]), "=f"(d[49]), "=f"(d[50]), "=f"(d[51]), "=f"(d[52]), "=f"(d[53]), "=f"(d[54]), "=f"(d[55]), "=f"(d[56]), "=f"(d[57]), "=f"(d[58]), "=f"(d[59]), "=f"(d[60]), "=f"(d[61]), "=f"(d[62]), "=f"(d[63]), "=f"(d[64]), "=f"(d[65]), "=f"(d[66]), "=f"(d[67]), "=f"(d[68]), "=f"(d[69]), "=f"(d[70]), "=f"(d[71]), "=f"(d[72]), "=f"(d[73]), "=f"(d[74]), "=f"(d[75]), "=f"(d[76]), "=f"(d[77]), "=f"(d[78]), "=f"(d[79]), "=f"(d[80]), "=f"(d[81]), "=f"(d[82]), "=f"(d[83]), "=f"(d[84]), "=f"(d[85]), "=f"(d[86]), "=f"(d[87]), "=f"(d[88]), "=f"(d[89]), "=f"(d[90]), "=f"(d[91]), "=f"(d[92]), "=f"(d[93]), "=f"(d[94]), "=f"(d[95])
    : "r"(da), "r"(db));
}
__device__ __forceinline__ void wgmma_ss_n64(float (&d)[32], uint32_t da, uint32_t db, int scale_d) {
  asm volatile("{\n.reg .pred p;\n.reg .b64 da, db;\nsetp.ne.b32 p, %34, 0;\nmov.b64 da, {%32, 0x40000040};\nmov.b64 db, {%33, 0x40000040};\n"
    "wgmma.mma_async.sync.aligned.m64n64k16.f32.bf16.bf16 {%0, %1, %2, %3, %4, %5, %6, %7, %8, %9, %10, %11, %12, %13, %14, %15, %16, %17, %18, %19, %20, %21, %22, %23, %24, %25, %26, %27, %28, %29, %30, %31}, da, db, p, 1, 1, 0, 1;\n}\n"
    : "+f"(d[0]), "+f"(d[1]), "+f"(d[2]), "+f"(d[3]), "+f"(d[4]), "+f"(d[5]), "+f"(d[6]), "+f"(d[7]), "+f"(d[8]), "+f"(d[9]), "+f"(d[10]), "+f"(d[11]), "+f"(d[12]), "+f"(d[13]), "+f"(d[14]), "+f"(d[15]), "+f"(d[16]), "+f"(d[17]), "+f"(d[18]), "+f"(d[19]), "+f"(d[20]), "+f"(d[21]), "+f"(d[22]), "+f"(d[23]), "+f"(d[24]), "+f"(d[25]), "+f"(d[26]), "+f"(d[27]), "+f"(d[28]), "+f"(d[29]), "+f"(d[30]), "+f"(d[31])
    : "r"(da), "r"(db), "r"(scale_d));
}
__device__ __forceinline__ void wgmma_rs_n192(float (&d)[96], uint32_t a0, uint32_t a1, uint32_t a2, uint32_t a3, uint32_t db, int scale_d) {
  asm volatile("{\n.reg .pred p;\n.reg .b64 db;\nsetp.ne.b32 p, %101, 0;\nmov.b64 db, {%100, 0x40000040};\n"
    "wgmma.mma_async.sync.aligned.m64n192k16.f32.bf16.bf16 {%0, %1, %2, %3, %4, %5, %6, %7, %8, %9, %10, %11, %12, %13, %14, %15, %16, %17, %18, %19, %20, %21, %22, %23, %24, %25, %26, %27, %28, %29, %30, %31, %32, %33, %34, %35, %36, %37, %38, %39, %40, %41, %42, %43, %44, %45, %46, %47, %48, %49, %50, %51, %52, %53, %54, %55, %56, %57, %58, %59, %60, %61, %62, %63, %64, %65, %66, %67, %68, %69, %70, %71, %72, %73, %74, %75, %76, %77, %78, %79, %80, %81, %82, %83, %84, %85, %86, %87, %88, %89, %90, %91, %92, %93, %94, %95}, {%96, %97, %98, %99}, db, p, 1, 1, 1;\n}\n"
    : "+f"(d[0]), "+f"(d[1]), "+f"(d[2]), "+f"(d[3]), "+f"(d[4]), "+f"(d[5]), "+f"(d[6]), "+f"(d[7]), "+f"(d[8]), "+f"(d[9]), "+f"(d[10]), "+f"(d[11]), "+f"(d[12]), "+f"(d[13]), "+f"(d[14]), "+f"(d[15]), "+f"(d[16]), "+f"(d[17]), "+f"(d[18]), "+f"(d[19]), "+f"(d[20]), "+f"(d[21]), "+f"(d[22]), "+f"(d[23]), "+f"(d[24]), "+f"(d[25]), "+f"(d[26]), "+f"(d[27]), "+f"(d[28]), "+f"(d[29]), "+f"(d[30]), "+f"(d[31]), "+f"(d[32]), "+f"(d[33]), "+f"(d[34]), "+f"(d[35]), "+f"(d[36]), "+f"(d[37]), "+f"(d[38]), "+f"(d[39]), "+f"(d[40]), "+f"(d[41]), "+f"(d[42]), "+f"(d[43]), "+f"(d[44]), "+f"(d[45]), "+f"(d[46]), "+f"(d[47]), "+f"(d[48]), "+f"(d[49]), "+f"(d[50]), "+f"(d[51]), "+f"(d[52]), "+f"(d[53]), "+f"(d[54]), "+f"(d[55]), "+f"(d[56]), "+f"(d[57]), "+f"(d[58]), "+f"(d[59]), "+f"(d[60]), "+f"(d[61]), "+f"(d[62]), "+f"(d[63]), "+f"(d[64]), "+f"(d[65]), "+f"(d[66]), "+f"(d[67]), "+f"(d[68]), "+f"(d[69]), "+f"(d[70]), "+f"(d[71]), "+f"(d[72]), "+f"(d[73]), "+f"(d[74]), "+f"(d[75]), "+f"(d[76]), "+f"(d[77]), "+f"(d[78]), "+f"(d[79]), "+f"(d[80]), "+f"(d[81]), "+f"(d[82]), "+f"(d[83]), "+f"(d[84]), "+f"(d[85]), "+f"(d[86]), "+f"(d[87]), "+f"(d[88]), "+f"(d[89]), "+f"(d[90]), "+f"(d[91]), "+f"(d[92]), "+f"(d[93]), "+f"(d[94]), "+f"(d[95])
    : "r"(a0), "r"(a1), "r"(a2), "r"(a3), "r"(db), "r"(scale_d));
}
__device__ __forceinline__ void wgmma_rt_n24(float (&d)[12], uint32_t a0, uint32_t a1, uint32_t a2, uint32_t a3, uint32_t db, int scale_d) {
  asm volatile("{\n.reg .pred p;\n.reg .b64 db;\nsetp.ne.b32 p, %17, 0;\nmov.b64 db, {%16, 0x30};\n"
    "wgmma.mma_async.sync.aligned.m64n24k16.f32.bf16.bf16 {%0, %1, %2, %3, %4, %5, %6, %7, %8, %9, %10, %11}, {%12, %13, %14, %15}, db, p, 1, 1, 1;\n}\n"
    : "+f"(d[0]), "+f"(d[1]), "+f"(d[2]), "+f"(d[3]), "+f"(d[4]), "+f"(d[5]), "+f"(d[6]), "+f"(d[7]), "+f"(d[8]), "+f"(d[9]), "+f"(d[10]), "+f"(d[11])
    : "r"(a0), "r"(a1), "r"(a2), "r"(a3), "r"(db), "r"(scale_d));
}
__device__ __forceinline__ void wgmma_rs_n64(float (&d)[32], uint32_t a0, uint32_t a1, uint32_t a2, uint32_t a3, uint32_t db, int scale_d) {
  asm volatile("{\n.reg .pred p;\n.reg .b64 db;\nsetp.ne.b32 p, %37, 0;\nmov.b64 db, {%36, 0x40000040};\n"
    "wgmma.mma_async.sync.aligned.m64n64k16.f32.bf16.bf16 {%0, %1, %2, %3, %4, %5, %6, %7, %8, %9, %10, %11, %12, %13, %14, %15, %16, %17, %18, %19, %20, %21, %22, %23, %24, %25, %26, %27, %28, %29, %30, %31}, {%32, %33, %34, %35}, db, p, 1, 1, 1;\n}\n"
    : "+f"(d[0]), "+f"(d[1]), "+f"(d[2]), "+f"(d[3]), "+f"(d[4]), "+f"(d[5]), "+f"(d[6]), "+f"(d[7]), "+f"(d[8]), "+f"(d[9]), "+f"(d[10]), "+f"(d[11]), "+f"(d[12]), "+f"(d[13]), "+f"(d[14]), "+f"(d[15]), "+f"(d[16]), "+f"(d[17]), "+f"(d[18]), "+f"(d[19]), "+f"(d[20]), "+f"(d[21]), "+f"(d[22]), "+f"(d[23]), "+f"(d[24]), "+f"(d[25]), "+f"(d[26]), "+f"(d[27]), "+f"(d[28]), "+f"(d[29]), "+f"(d[30]), "+f"(d[31])
    : "r"(a0), "r"(a1), "r"(a2), "r"(a3), "r"(db), "r"(scale_d));
}
__device__ __forceinline__ void wgmma_rl_n64(float (&d)[32], uint32_t a0, uint32_t a1, uint32_t a2, uint32_t a3, uint64_t db, int scale_d) {
  asm volatile("{\n.reg .pred p;\nsetp.ne.b32 p, %37, 0;\n"
    "wgmma.mma_async.sync.aligned.m64n64k16.f32.bf16.bf16 {%0, %1, %2, %3, %4, %5, %6, %7, %8, %9, %10, %11, %12, %13, %14, %15, %16, %17, %18, %19, %20, %21, %22, %23, %24, %25, %26, %27, %28, %29, %30, %31}, {%32, %33, %34, %35}, %36, p, 1, 1, 1;\n}\n"
    : "+f"(d[0]), "+f"(d[1]), "+f"(d[2]), "+f"(d[3]), "+f"(d[4]), "+f"(d[5]), "+f"(d[6]), "+f"(d[7]), "+f"(d[8]), "+f"(d[9]), "+f"(d[10]), "+f"(d[11]), "+f"(d[12]), "+f"(d[13]), "+f"(d[14]), "+f"(d[15]), "+f"(d[16]), "+f"(d[17]), "+f"(d[18]), "+f"(d[19]), "+f"(d[20]), "+f"(d[21]), "+f"(d[22]), "+f"(d[23]), "+f"(d[24]), "+f"(d[25]), "+f"(d[26]), "+f"(d[27]), "+f"(d[28]), "+f"(d[29]), "+f"(d[30]), "+f"(d[31])
    : "r"(a0), "r"(a1), "r"(a2), "r"(a3), "l"(db), "r"(scale_d));
}

__device__ __forceinline__ void mma_k16(float (&d)[4], uint32_t a0, uint32_t a1, uint32_t a2, uint32_t a3, uint32_t b0, uint32_t b1) {
  asm("mma.sync.aligned.m16n8k16.row.col.f32.bf16.bf16.f32 {%0,%1,%2,%3}, {%4,%5,%6,%7}, {%8,%9}, {%0,%1,%2,%3};"
      : "+f"(d[0]), "+f"(d[1]), "+f"(d[2]), "+f"(d[3]) : "r"(a0), "r"(a1), "r"(a2), "r"(a3), "r"(b0), "r"(b1));
}
__device__ __forceinline__ void mma_k8(float (&d)[4], uint32_t a0, uint32_t a1, uint32_t b0) {
  asm("mma.sync.aligned.m16n8k8.row.col.f32.bf16.bf16.f32 {%0,%1,%2,%3}, {%4,%5}, {%6}, {%0,%1,%2,%3};"
      : "+f"(d[0]), "+f"(d[1]), "+f"(d[2]), "+f"(d[3]) : "r"(a0), "r"(a1), "r"(b0));
}
__device__ __forceinline__ uint32_t movm_t(uint32_t a) {
  uint32_t d;
  asm("movmatrix.sync.aligned.m8n8.trans.b16 %0, %1;" : "=r"(d) : "r"(a));
  return d;
}
__device__ __forceinline__ void lds128(uint32_t a, uint32_t& x, uint32_t& y, uint32_t& z, uint32_t& w) {
  asm volatile("ld.shared.v4.u32 {%0, %1, %2, %3}, [%4];" : "=r"(x), "=r"(y), "=r"(z), "=r"(w) : "r"(a) : "memory");
}
__device__ __forceinline__ void cp_async16(uint32_t dst, const void* src) {
  asm volatile("cp.async.cg.shared.global [%0], [%1], 16;" ::"r"(dst), "l"(src) : "memory");
}
__device__ __forceinline__ float rcp(float v) {
  float r;
  asm("rcp.approx.ftz.f32 %0, %1;" : "=f"(r) : "f"(v));
  return r;
}
__device__ __forceinline__ float sqrt_fast(float v) {
  float r;
  asm("sqrt.approx.ftz.f32 %0, %1;" : "=f"(r) : "f"(v));
  return r;
}
__device__ __forceinline__ float ex2(float v) {
  float r;
  asm("ex2.approx.ftz.f32 %0, %1;" : "=f"(r) : "f"(v));
  return r;
}

__device__ __forceinline__ void acc_bf16x8(float* s, const uint4& v) {
  s[0] += bf_lo(v.x); s[1] += bf_hi(v.x); s[2] += bf_lo(v.y); s[3] += bf_hi(v.y);
  s[4] += bf_lo(v.z); s[5] += bf_hi(v.z); s[6] += bf_lo(v.w); s[7] += bf_hi(v.w);
}

#define PIN1(A) \
  asm volatile("{\n.reg .pred p;\nsetp.eq.u32 p, %1, 0;\n@p st.shared.u32 [%1], %0;\n}\n" ::"r"(A), "r"(gridDim.x) : "memory")
constexpr int BAR_TURN0 = 1;
constexpr int BAR_WG0 = 3;
constexpr int BAR_HELP = 5;

__global__ void __cluster_dims__(2, 1, 1) __launch_bounds__(384, 1)
fused_kernel(const __grid_constant__ CUtensorMap tm_x, const __grid_constant__ CUtensorMap tm_wqkv,
             const __grid_constant__ CUtensorMap tm_wtail,
             const __grid_constant__ CUtensorMap tm_w1, const __grid_constant__ CUtensorMap tm_w2,
             const __grid_constant__ CUtensorMap tm_wo,
             const __nv_bfloat16* __restrict__ x, const __nv_bfloat16* __restrict__ wqkv,
             const __nv_bfloat16* __restrict__ wo, const __nv_bfloat16* __restrict__ w1,
             const __nv_bfloat16* __restrict__ b1, const __nv_bfloat16* __restrict__ w2,
             const __nv_bfloat16* __restrict__ b2, __nv_bfloat16* __restrict__ out) {
  extern __shared__ uint8_t smem_raw[];
  constexpr uint32_t kBase = 1024, kBars = kBase + OFF_MISC;
  const uint32_t rank = blockIdx.x & 1;
  const uint32_t base = smem_u32(smem_raw);
  if (base != ((rank << 24) | kBase)) return;
  const uint32_t bars = base + OFF_MISC;
  const int tid = threadIdx.x;
  const int warp = __shfl_sync(0xffffffff, tid >> 5, 0);
  const int lane = tid & 31;
  const int mt = blockIdx.x & 15, j = blockIdx.x >> 4;
  uint4* const scr = g_scr + mt * SC_SIZE;

  if (warp < 8) {
    const int r = lane >> 3, c = lane & 7;
    const char* src = reinterpret_cast<const char*>(x + (mt * 128 + (warp & 3) * 32 + 2 * r + (warp >> 2)) * kD) + c * 16;
    const uint32_t dst = base + (warp * 16 + r) * 128;
#pragma unroll 1
    for (int kb = 0; kb < 9; kb++) {
#pragma unroll
      for (int i = 0; i < 4; i++) cp_async16(dst + kb * 16384 + i * 512 + ((c ^ ((r + 4 * i) & 7)) << 4), src + kb * 128 + i * (16 * kD));
      asm volatile("cp.async.commit_group;" ::: "memory");
    }
  } else if (warp == 9) {
    if (elect_one()) {
      prefetch_tmap(&tm_wqkv);
      prefetch_tmap(&tm_wtail);
#pragma unroll
      for (int i = 0; i < N_BAR; i++) mbar_init(bars + 8 * i, 8 * i < B_EMPTY1 ? 1 : (8 * i < B_XDONE ? 16 : 8));
      asm volatile("fence.mbarrier_init.release.cluster;" ::: "memory");
    }
  }
  __syncthreads();
  asm volatile("barrier.cluster.arrive.relaxed.aligned;" ::: "memory");
  PROF(0);

  if (warp >= 8) {
    asm volatile("setmaxnreg.dec.sync.aligned.u32 %0;" ::"n"(HELP_REGS));
    asm volatile("barrier.cluster.wait.acquire.aligned;" ::: "memory");
    if (warp == 8) {
      PROF(1);
      uint32_t so = 0, ph = 1;
      auto next_slot = [&]() { so += 8; if (so == 24) { so = 0; ph ^= 1; } };
#pragma unroll 1
      for (int st = 0; st < 12; st++) {
        const uint32_t dst = base + OFF_RING + so * (SLOT / 8), fb = bars + B_FULL1 + so;
        if (st == 1) mbar_wait(bars + B_XDONE, 0);
        mbar_wait(bars + B_EMPTY1 + so, ph);
        if (elect_one()) {
          mbar_expect_tx(fb, 3 * 6144 + 3 * 768);
          tma_mc_2d(dst + rank * 12288, &tm_wqkv, j * 72 + rank * 2 * kD, st * 48, fb);
          if (rank == 0) {
            tma_mc_2d(dst + 6144, &tm_wqkv, j * 72 + kD, st * 48, fb);
          } else {
#pragma unroll
            for (int w = 0; w < 3; w++) tma_mc_2d(dst + 3 * 6144 + w * 768, &tm_wtail, j * 72 + 64 + w * kD, st * 48, fb);
          }
          if (st == 2) { prefetch_tmap(&tm_x); prefetch_tmap(&tm_w1); prefetch_tmap(&tm_w2); prefetch_tmap(&tm_wo); }
        }
        next_slot();
      }
      int col1 = j * 576, row1 = rank * 32;
#pragma unroll 1
      for (int st = 0; st < 27; st++) {
        const uint32_t dst = base + OFF_RING + so * (SLOT / 8) + rank * 4096, fb = bars + B_FULL1 + so;
        mbar_wait(bars + B_EMPTY1 + so, ph);
        if (elect_one()) {
          mbar_expect_tx(fb, SLOT);
#pragma unroll
          for (int b = 0; b < 3; b++) tma_mc_2d(dst + b * 8192, &tm_w1, col1 + b * 64, row1, fb);
          if (st >= 22 && !(st & 1)) {
            if (st == 22) mbar_expect_tx(bars + B_FULL2, 3 * SLOT + 10240);
            tma_mc_2d(base + ((st - 22) >> 1) * SLOT + rank * 12288, &tm_w2, 512, j * 576 + ((st - 22) >> 1) * 192 + rank * 96, bars + B_FULL2);
            if (st == 26) tma_mc_2d(base + OFF_WO + rank * 5120, &tm_wo, 512, j * 72 + rank * 40, bars + B_FULL2);
          }
        }
        row1 += 64;
        if (row1 >= kD) { row1 -= kD; col1 += 192; }
        next_slot();
      }
#pragma unroll 1
      for (int st = 0; st < 3; st++) {
        mbar_wait(bars + B_EMPTY1 + 8 * st, ph);
        if (elect_one()) {
          if (st == 0) {
            mbar_expect_tx(bars + B_FULL2 + 8, 3 * SLOT + 10240);
            tma_mc_2d(base + OFF_WO + 10240 + rank * 5120, &tm_wo, ((j + 1) & 7) * 64, j * 72 + rank * 40, bars + B_FULL2 + 8);
          }
          tma_mc_2d(base + OFF_RING + st * SLOT + rank * 12288, &tm_w2, ((j + 1) & 7) * 64, j * 576 + st * 192 + rank * 96, bars + B_FULL2 + 8);
        }
      }
#pragma unroll 1
      for (int t = 2; t < 9; t++) {
        const int col = ((j + t) & 7) * 64;
        const int hb = t & 1;
        const uint32_t pe = ((t >> 1) & 1) ^ 1;
        const uint32_t dst = base + (hb ? OFF_RING : 0) + rank * 12288, fb = bars + B_FULL2 + 8 * hb;
        const int row = j * 576 + rank * 96;
        mbar_wait(bars + B_EMPTY2 + 16 * hb, pe);
        if (elect_one()) {
          mbar_expect_tx(bars + B_FULL2 + 8 * hb, 3 * SLOT + 10240 + (t == 2 ? 16384 : 0));
          tma_mc_2d(dst, &tm_w2, col, row, fb);
          tma_mc_2d(dst + SLOT, &tm_w2, col, row + 192, fb);
        }
        mbar_wait(bars + B_EMPTY2 + 16 * hb + 8, pe);
        if (elect_one()) {
          tma_mc_2d(dst + 2 * SLOT, &tm_w2, col, row + 384, fb);
          tma_mc_2d(base + OFF_WO + hb * 10240 + rank * 5120, &tm_wo, col, j * 72 + rank * 40, fb);
          if (t == 2) {
            tma_load_2d(base + OFF_XT, &tm_x, col, mt * 64, fb);
            tma_load_2d(base + OFF_XT + 8192, &tm_x, kD + col, mt * 64, fb);
          }
        }
      }
    } else {
      const int hw = warp - 9, ht = hw * 32 + lane;
      if (ht < 36) l2_prefetch(wqkv + (size_t)(mt * 36 + ht) * kQKV + j * 216, 432);
      unsigned* const sync = reinterpret_cast<unsigned*>(scr + SC_SYNC);
      const unsigned epoch = sync[64 + j] + 1;
#pragma unroll 1
      for (int e = ht; e < 288; e += 96) {
        int c = e / 96, t = ht / 24, i = ht % 24;
        uint32_t v = *reinterpret_cast<const uint32_t*>(b1 + j * 576 + c * 192 + i * 8 + t * 2);
        asm volatile("st.shared.u32 [%0], %1;" ::"r"(base + OFF_BIAS + e * 4), "r"(v) : "memory");
      }
      if (hw == 2) {
        uint32_t v = *reinterpret_cast<const uint32_t*>(b2 + ((j + 1) & 7) * 64 + lane * 2);
        asm volatile("st.shared.u32 [%0], %1;" ::"r"(base + OFF_B2 + lane * 4), "r"(v) : "memory");
      }
      bar_sync(BAR_HELP, 96);
      if (hw == 0) {
        if (lane == 0) {
          asm volatile("st.shared.u32 [%0], %1;" ::"r"(base + OFF_EPOCH), "r"(epoch) : "memory");
          mbar_arrive(bars + B_BIAS);
        }
        mbar_wait(bars + B_PART, 0);
        if (lane == 0) {
          fence_gpu();
          asm volatile("st.relaxed.gpu.global.u32 [%0], %1;" ::"l"(sync + 32 + j), "r"(epoch) : "memory");
          sync[64 + j] = epoch;
        }
      } else {
        mbar_wait(bars + B_XDONE, 0);
#pragma unroll 1
        for (int i = lane + (hw - 1) * 32; i < 36 * 9; i += 64)
          asm volatile("prefetch.global.L2 [%0];" ::"l"(w1 + (size_t)(mt * 36 + i / 9) * kF + j * 576 + (i % 9) * 64));
        PROFW(9);
      }
      {
        if (hw == 1) {
          mbar_wait(bars + B_PART, 0);
          __nanosleep(1000);
          if (lane < 8) poll_ge(sync + 32 + lane, epoch);
        }
        bar_sync(BAR_HELP, 96);
        const uint32_t land = base + OFF_S8 + hw * 4096 + lane * 16;
        const int eo = (mt * 128 + (j & 3) * 32 + (lane >> 2) * 2 + (j >> 2)) * kD + 512 + (lane & 3) * 2;
#pragma unroll 1
        for (int q = hw; q < 4; q += 3) {
          const uint4* pp = scr + (SC_PART + j * 128 + q * 32 + lane);
#pragma unroll
          for (int src = 0; src < 8; src++) cp_async16(land + src * 512, pp + src * 1024);
          float s[8];
          {
            const __nv_bfloat16* bp = b2 + 512 + q * 16 + (lane & 3) * 2;
            const __nv_bfloat16* xp = x + eo + q * 16;
            uint4 v;
            uint32_t ba = *reinterpret_cast<const uint32_t*>(bp), bb = *reinterpret_cast<const uint32_t*>(bp + 8);
            v.x = *reinterpret_cast<const uint32_t*>(xp);
            v.y = *reinterpret_cast<const uint32_t*>(xp + 16 * kD);
            v.z = *reinterpret_cast<const uint32_t*>(xp + 8);
            v.w = *reinterpret_cast<const uint32_t*>(xp + 16 * kD + 8);
            s[0] = s[2] = bf_lo(ba); s[1] = s[3] = bf_hi(ba);
            s[4] = s[6] = bf_lo(bb); s[5] = s[7] = bf_hi(bb);
            acc_bf16x8(s, v);
          }
          asm volatile("cp.async.wait_all;" ::: "memory");
#pragma unroll 2
          for (int src = 0; src < 8; src++) {
            uint4 v;
            lds128(land + src * 512, v.x, v.y, v.z, v.w);
            acc_bf16x8(s, v);
          }
          __nv_bfloat16* op = out + eo + q * 16;
          *reinterpret_cast<uint32_t*>(op) = pack_bf16(s[0], s[1]);
          *reinterpret_cast<uint32_t*>(op + 16 * kD) = pack_bf16(s[2], s[3]);
          *reinterpret_cast<uint32_t*>(op + 8) = pack_bf16(s[4], s[5]);
          *reinterpret_cast<uint32_t*>(op + 16 * kD + 8) = pack_bf16(s[6], s[7]);
        }
      }
      PROFW(hw * 4 + 3);
    }
  } else {
    asm volatile("setmaxnreg.inc.sync.aligned.u32 %0;" ::"n"(CONS_REGS));
    const int wg = warp >> 2;
    const int g = lane >> 2, tq = lane & 3;
    if (wg == 1) bar_arrive(BAR_TURN0, 256);
    const uint32_t rel0 = kBars + ((uint32_t)lane << 24), relE = rel0 + B_EMPTY2;
    const int lrow = warp * 16 + ((lane >> 3) & 1) * 8 + (lane & 7);
    const uint32_t lm_base = base + lrow * 128;
    const uint32_t lm_x = (lane >> 4), lm_sw = lane & 7;
    asm volatile("barrier.cluster.wait.acquire.aligned;" ::: "memory");
    float mu0, rs0, mu1, rs1;
    uint32_t raw[3][4];
    {
      float sm[2][4], g0[2][4], g1[2][4];
#pragma unroll
      for (int i = 0; i < 8; i++) sm[i >> 2][i & 3] = g0[i >> 2][i & 3] = g1[i >> 2][i & 3] = 0.f;
#pragma unroll 1
      for (int kb = 0; kb < 9; kb++) {
        asm volatile("cp.async.wait_group 8;\ncp.async.commit_group;" ::: "memory");
        __syncwarp();
        if (kb == 7 && lane == 0) mbar_arrive(bars + B_XDONE);
        uint32_t r[4][4];
#pragma unroll
        for (int k = 0; k < 4; k++) ldsm_x4(r[k], lm_base + kb * 16384 + (((k * 2 + lm_x) ^ lm_sw) << 4));
#pragma unroll
        for (int k = 0; k < 4; k++) {
          mma_k16(sm[k & 1], r[k][0], r[k][1], r[k][2], r[k][3], 0x3f803f80u, 0x3f803f80u);
          mma_k16(g0[k & 1], r[k][0], r[k][1], r[k][2], r[k][3], r[k][0], r[k][2]);
          mma_k16(g1[k & 1], r[k][0], r[k][1], r[k][2], r[k][3], r[k][1], r[k][3]);
        }
      }
      PROF(11);
#pragma unroll
      for (int k = 0; k < 3; k++) ldsm_x4(raw[k], lm_base + (((k * 2 + lm_x) ^ lm_sw) << 4));
      const float s0 = sm[0][0] + sm[1][0], s1 = sm[0][2] + sm[1][2];
      const int dl = (lane & 28) | (g >> 1);
      const float q0 = __shfl_sync(0xffffffff, (g & 1) ? g0[0][1] + g0[1][1] : g0[0][0] + g0[1][0], dl);
      const float q1 = __shfl_sync(0xffffffff, (g & 1) ? g1[0][3] + g1[1][3] : g1[0][2] + g1[1][2], dl);
      const float inv = 1.f / kD;
      mu0 = s0 * inv; mu1 = s1 * inv;
      const uint32_t v = pack_bf16(fmaxf(q0 * inv - mu0 * mu0, 0.f), fmaxf(q1 * inv - mu1 * mu1, 0.f));
      const uint32_t e = pack_bf16(bf_lo(v) + 1e-5f, bf_hi(v) + 1e-5f);
      const uint32_t d = pack_bf16(sqrt_fast(bf_lo(e)), sqrt_fast(bf_hi(e)));
      rs0 = rcp(bf_lo(d)); rs1 = rcp(bf_hi(d));
    }
    PROF(1);
#define TURN_TAKE(n) do { bar_sync(BAR_TURN0 + wg, 256); wgmma_fence(); TL(n); } while (0)
#define TURN_GIVE() do { wgmma_commit(); bar_arrive(BAR_TURN0 + (wg ^ 1), 256); } while (0)
#define GROUP_END(EMPTY, NEXTFULL, NEXTPAR)                    \
  do {                                                         \
    const bool rdy_ = mbar_test_wait(NEXTFULL, NEXTPAR);       \
    wgmma_wait<0>();                                           \
    release_pair(EMPTY, true);                                 \
    if (!rdy_) mbar_wait(NEXTFULL, NEXTPAR);                   \
  } while (0)

#define RING_END()                                                                   \
  do {                                                                               \
    const int sn_ = slot == 2 ? 0 : slot + 1;                                        \
    ph ^= slot == 2;                                                                 \
    GROUP_END(rel0 + B_EMPTY1 + 8 * slot, bars + B_FULL1 + 8 * sn_, ph);             \
    slot = sn_;                                                                      \
  } while (0)
    int slot = 0;
    uint32_t ph = 0;
    float qacc[96], qtail[12];
    uint32_t tag0 = 0;
    {
      uint32_t a[2][3][4];
      const uint32_t nh0 = pack_bf16(rs0, rs0), nl0 = pack_bf16(rs0 - bf_lo(nh0), rs0 - bf_lo(nh0)), nm0 = pack_bf16(-mu0, -mu0);
      const uint32_t nh1 = pack_bf16(rs1, rs1), nl1 = pack_bf16(rs1 - bf_lo(nh1), rs1 - bf_lo(nh1)), nm1 = pack_bf16(-mu1, -mu1);
      auto norm2 = [&](uint32_t w, uint32_t nh, uint32_t nl, uint32_t nm) {
        const uint32_t c = fma2(w, 0x3f803f80u, nm);
        return fma2(c, nh, fma2(c, nl, 0x80008000u));
      };
      auto frag_addr = [&](uint32_t xb, int kk) { return xb + (kk >> 2) * 16384 + ((((kk & 3) * 2 + lm_x) ^ lm_sw) << 4); };
      auto prep = [&](uint32_t (&an)[3][4], uint32_t xb, int kk0) {
#pragma unroll
        for (int k = 0; k < 3; k++) {
          an[k][0] = norm2(raw[k][0], nh0, nl0, nm0);
          an[k][1] = norm2(raw[k][1], nh1, nl1, nm1);
          an[k][2] = norm2(raw[k][2], nh0, nl0, nm0);
          an[k][3] = norm2(raw[k][3], nh1, nl1, nm1);
          stsm_x4(frag_addr(xb, kk0 + k), an[k][0], an[k][1], an[k][2], an[k][3]);
        }
      };
      prep(a[0], lm_base, 0);
      mbar_wait(bars + B_FULL1, 0);
#pragma unroll 1
      for (int it = 0; it < 3; it++) {
#pragma unroll
        for (int u = 0; u < 4; u++) {
          const uint32_t db = make_desc(kBase + OFF_RING, 6144) + slot * (SLOT >> 4);
          const uint32_t dt = make_desc(kBase + OFF_RING + 3 * 6144, 128) + slot * (SLOT >> 4);
#pragma unroll
          for (int k = 0; k < 3; k++) ldsm_x4(raw[k], frag_addr(lm_base + it * 49152, u * 3 + 3 + k));
          TURN_TAKE(it * 4 + u);
#pragma unroll
          for (int k = 0; k < 3; k++) {
            wgmma_rs_n192(qacc, a[u & 1][k][0], a[u & 1][k][1], a[u & 1][k][2], a[u & 1][k][3], db + k * 128, (it | u | k) != 0);
            wgmma_rt_n24(qtail, a[u & 1][k][0], a[u & 1][k][1], a[u & 1][k][2], a[u & 1][k][3], dt + k * 16, (it | u | k) != 0);
          }
          TURN_GIVE();
          if (gridDim.y == 0) __nanosleep(1);
          if (u < 3 || it < 2) prep(a[(u + 1) & 1], lm_base + it * 49152, u * 3 + 3);
          RING_END();
        }
      }
      asm volatile("fence.proxy.async.shared::cta;" ::: "memory");
      fence_regs(qacc);
      fence_regs(qtail);
    }
    PROF(2);
    uint32_t hf[144];
    constexpr uint32_t dB = make_desc(kBase, 8192);
    const uint32_t dA = make_desc(kBase, 16) + wg * 512;
    uint32_t aq[24], ak[27], av[27], pa[4][4], of[18];
    float S[4][3][4], sv[4][4], mx[4][2];
    uint4 hv[3];
    uint4* ofp = scr + (SC_OF + j * 1280 + tid);
    const uint32_t ofl = base + OFF_XT + wg * 8192 + (tid & 127) * 16;
    const bool edge = mt == 0 && (warp & 3) == 0;
    const uint4* hsrc = scr + (SC_HALO + j * 1536 + tid + ((warp & 3) ? -32 : (mt ? 96 - SC_SIZE : 0)));
    uint4* hdst = scr + (SC_HALO + j * 1536 + tid);
    auto halo_load = [&](int q0) {
#pragma unroll
      for (int q = 0; q < 3; q++) hv[q] = ld_b128(hsrc + (q0 + q) * 256);
    };
    auto halo_check = [&](int q0) {
#pragma unroll 1
      for (int it = 0; it < (1 << 16); it++) {
        if (__all_sync(0xffffffff, hv[0].w == tag0 && hv[1].w == tag0 && hv[2].w == tag0)) break;
        halo_load(q0);
      }
    };
    auto qkv_word = [&](int which, int p, int half) {
      const float* a = p < 8 ? qacc + 4 * (which * 8 + (p & 7)) : qtail + 4 * which;
      return pack_bf16(a[2 * half], a[2 * half + 1]);
    };
    const bool c0 = 2 * tq > g, c1 = 2 * tq + 1 > g;
    const uint32_t M = (c0 ? 0xffffu : 0u) | (c1 ? 0xffff0000u : 0u);
    float acc0[96], acc1[96];
    auto activate = [&](int c, int part) {
#pragma unroll
      for (int i4 = part * 2; i4 < part * 2 + 2; i4++) {
        uint32_t bw[4];
        lds128(base + OFF_BIAS + (c * 96 + tq * 24 + i4 * 4) * 4, bw[0], bw[1], bw[2], bw[3]);
#pragma unroll
        for (int i = 0; i < 8; i++) {
          if (c == 0) hf[i4 * 8 + i] = pack_bf16(acc0[2 * (i4 * 8 + i)], acc0[2 * (i4 * 8 + i) + 1]);
          asm volatile("fma.rn.relu.bf16x2 %0, %0, %1, %2;\nmul.rn.bf16x2 %0, %0, %0;"
                       : "+r"(hf[c * 48 + i4 * 8 + i]) : "r"(0x3f803f80u), "r"(bw[i >> 1]));
        }
      }
    };
#pragma unroll
    for (int c = 0; c < 3; c++) {
      float (&acc)[96] = c == 0 ? acc0 : acc1;
      constexpr int kHead[3] = {AT_O + 1, 4, 2};
#pragma unroll
      for (int it = 0; it < 3; it++) {
#pragma unroll
        for (int s = 0; s < 3; s++) {
          const int kb = it * 3 + s;
          if (kb >= kHead[c]) continue;
          const uint32_t db = dB + ((OFF_RING + s * SLOT) >> 4);
          const uint32_t da = dA;
          if (c == 0 && (kb == AT_S || kb == AT_O)) {
            uint32_t z = 0;
#pragma unroll
            for (int h = 0; h < 4; h++)
#pragma unroll
              for (int n = 0; n < 3; n++) {
                S[h][n][0] = S[h][n][1] = S[h][n][2] = S[h][n][3] = 0.f;
                if (kb == AT_S) {
                  mma_k16(S[h][n], aq[6 * h], aq[6 * h + 1], aq[6 * h + 2], aq[6 * h + 3], ak[6 * h + n], ak[6 * h + 3 + n]);
                  mma_k8(S[h][n], aq[6 * h + 4], aq[6 * h + 5], ak[6 * h + 6 + n]);
                } else {
                  mma_k16(S[h][n], pa[h][0], 0u, pa[h][1], pa[h][2], av[6 * h + 3 * n], av[6 * h + 3 * n + 1]);
                  mma_k8(S[h][n], 0u, pa[h][3], av[6 * h + 3 * n + 2]);
                }
                z ^= __float_as_uint(S[h][n][n == 0 ? 0 : 2]);
              }
            PIN1(z);
            if (wg == 1) bar_arrive(BAR_TURN0, 256);
          }
          TURN_TAKE(12 + c * 9 + kb);
#pragma unroll
          for (int k = 0; k < 4; k++) {
            if ((kb | k) == 0 && c < 2) wgmma_ss0_n192(acc, da, db);
            else wgmma_ss_n192(acc, da + kb * 1024 + k * 2, db + k * 128, (kb | k) != 0);
          }
          wgmma_commit();
          if (!(c == 0 && (kb == AT_S - 1 || kb == AT_O - 1)) || wg == 0) bar_arrive(BAR_TURN0 + (wg ^ 1), 256);
          if (c > 0) {
            if (c == 2 || kb >= 1) activate(c - 1, c == 2 ? kb : kb - 1);
            if (c == 2 && kb == 1) activate(1, 2);
          } else if (kb == 0) {
            mbar_wait_async(bars + B_BIAS, 0);
            asm volatile("ld.shared.u32 %0, [%1];" : "=r"(tag0) : "r"(base + OFF_EPOCH) : "memory");
#pragma unroll
            for (int p = 0; p < 9; p++) ak[3 * p + 2] = qkv_word(1, p, 1);
#pragma unroll
            for (int q = 0; q < 3; q++) st_b128(hdst + q * 256, ak[9 * q + 2], ak[9 * q + 5], ak[9 * q + 8], tag0);
          } else if (kb == 1) {
#pragma unroll
            for (int p = 0; p < 9; p++) av[3 * p + 2] = movm_t(qkv_word(2, p, 1));
#pragma unroll
            for (int q = 0; q < 3; q++) st_b128(hdst + (q + 3) * 256, av[9 * q + 2], av[9 * q + 5], av[9 * q + 8], tag0);
          } else if (kb == 2) {
            halo_load(0);
            uint32_t z = 0;
#pragma unroll
            for (int h = 0; h < 4; h++)
#pragma unroll
              for (int i = 0; i < 6; i++) {
                aq[6 * h + i] = (i < 2 ? tq >= h : (i >= 4 ? tq <= h : true)) ? qkv_word(0, 2 * h + (i >> 1), i & 1) : 0u;
                z += aq[6 * h + i];
              }
            PIN1(z);
          } else if (kb == 3) {
            uint32_t z = 0;
#pragma unroll
            for (int p = 0; p < 9; p++) { ak[3 * p + 1] = qkv_word(1, p, 0); av[3 * p + 1] = movm_t(qkv_word(2, p, 0)); z ^= ak[3 * p + 1] ^ av[3 * p + 1]; }
            PIN1(z);
            halo_check(0);
#pragma unroll
            for (int q = 0; q < 3; q++) { ak[9 * q] = hv[q].x; ak[9 * q + 3] = hv[q].y; ak[9 * q + 6] = hv[q].z; }
          } else if (kb == AT_O - 1) {
            halo_check(3);
#pragma unroll
            for (int q = 0; q < 3; q++) { av[9 * q] = hv[q].x; av[9 * q + 3] = hv[q].y; av[9 * q + 6] = hv[q].z; }
          } else if (kb == AT_S) {
            const float cs = 0.23570226039551584f * 1.4426950408889634f;
#pragma unroll
            for (int h = 0; h < 4; h++) {
              sv[h][0] = (c0 ? S[h][0][0] : S[h][1][0]) * cs; sv[h][1] = (c1 ? S[h][0][1] : S[h][1][1]) * cs;
              sv[h][2] = (c0 ? S[h][1][2] : S[h][2][2]) * cs; sv[h][3] = (c1 ? S[h][1][3] : S[h][2][3]) * cs;
              if (edge && c0) sv[h][0] = -1e9f * 1.4426950408889634f;
              if (edge && c1) sv[h][1] = -1e9f * 1.4426950408889634f;
              mx[h][0] = fmaxf(sv[h][0], sv[h][1]); mx[h][1] = fmaxf(sv[h][2], sv[h][3]);
            }
#pragma unroll
            for (int i = 0; i < 8; i++) mx[i >> 1][i & 1] = fmaxf(mx[i >> 1][i & 1], __shfl_xor_sync(0xffffffff, mx[i >> 1][i & 1], 1));
          } else if (kb == AT_S + 1) {
            halo_load(3);
#pragma unroll
            for (int i = 0; i < 8; i++) mx[i >> 1][i & 1] = fmaxf(mx[i >> 1][i & 1], __shfl_xor_sync(0xffffffff, mx[i >> 1][i & 1], 2));
#pragma unroll
            for (int h = 0; h < 4; h++) {
#pragma unroll
              for (int i = 0; i < 4; i++) sv[h][i] = ex2(sv[h][i] - mx[h][i >> 1]);
              mx[h][0] = sv[h][0] + sv[h][1]; mx[h][1] = sv[h][2] + sv[h][3];
            }
#pragma unroll
            for (int i = 0; i < 8; i++) mx[i >> 1][i & 1] += __shfl_xor_sync(0xffffffff, mx[i >> 1][i & 1], 1);
          } else if (kb == AT_S + 2) {
#pragma unroll
            for (int i = 0; i < 8; i++) mx[i >> 1][i & 1] += __shfl_xor_sync(0xffffffff, mx[i >> 1][i & 1], 2);
            uint32_t zz = 0;
#pragma unroll
            for (int h = 0; h < 4; h++) {
              const float za = rcp(mx[h][0]), zb = rcp(mx[h][1]);
              const uint32_t p0 = pack_bf16(sv[h][0] * za, sv[h][1] * za), p1 = pack_bf16(sv[h][2] * zb, sv[h][3] * zb);
              pa[h][0] = p0 & M; pa[h][1] = p0 & ~M; pa[h][2] = p1 & M; pa[h][3] = p1 & ~M;
              zz += (pa[h][0] + pa[h][2]) ^ (pa[h][1] + pa[h][3]);
            }
            PIN1(zz);
          } else if (kb == AT_O) {
#pragma unroll
            for (int h = 0; h < 4; h++)
#pragma unroll
              for (int n = 0; n < 3; n++) {
                const int p = 2 * h + n;
                const uint32_t o0 = pack_bf16(S[h][n][0], S[h][n][1]), o1 = pack_bf16(S[h][n][2], S[h][n][3]);
                if (n == 0 && h > 0) { of[2 * p] = tq >= h ? o0 : of[2 * p]; of[2 * p + 1] = tq >= h ? o1 : of[2 * p + 1]; }
                else { of[2 * p] = o0; of[2 * p + 1] = o1; }
              }
#pragma unroll
            for (int i = 0; i < 4; i++) ofp[i * 256] = make_uint4(of[4 * i], of[4 * i + 1], of[4 * i + 2], of[4 * i + 3]);
            ofp[4 * 256] = make_uint4(of[16], of[17], 0u, 0u);
          }
          GROUP_END(rel0 + B_EMPTY1 + 8 * s, bars + B_FULL1 + 8 * ((s + 1) % 3), ((c * 9 + kb + 1) / 3) & 1);
        }
      }
      slot = kHead[c] % 3;
      ph = ((c * 9 + kHead[c]) / 3) & 1;
#pragma unroll 1
      for (int kb = kHead[c]; kb < 9; kb++) {
        TURN_TAKE(12 + c * 9 + kb);
#pragma unroll
        for (int k = 0; k < 4; k++) wgmma_ss_n192(acc, dA + kb * 1024 + k * 2, dB + (OFF_RING >> 4) + slot * (SLOT >> 4) + k * 128, 1);
        TURN_GIVE();
        if (c == 2 && kb == 8) break;
        RING_END();
      }
      if (c == 2) GROUP_END(rel0 + B_EMPTY1 + 16, bars + B_FULL2, 0);
      fence_regs(acc);
      if (c == 2) {
#pragma unroll
        for (int i = 0; i < 5; i++) cp_async16(ofl + (i < 4 ? i * 2048 : -32768), ofp + i * 256);
      }
#pragma unroll
      for (int i = 47; i >= 0; i--) if (c > 0) hf[c * 48 + i] = pack_bf16(acc[2 * i], acc[2 * i + 1]);
      if (c == 2) {
        uint32_t z = 0;
#pragma unroll
        for (int i = 47; i >= 0; i--) z ^= hf[c * 48 + i];
        PIN1(z);
      }
      PROF(3 + c);
    }
    float acc[32];
    uint4 of4;
    constexpr uint64_t dB64 = (0x40000040ull << 32) + dB;

#define P2_MMA(KK, DB, DW)                                                                             \
  do {                                                                                                 \
    if ((KK) < 36) wgmma_rl_n64(acc, hf[((KK) % 36) * 4], hf[((KK) % 36) * 4 + 1], hf[((KK) % 36) * 4 + 2], hf[((KK) % 36) * 4 + 3], (DB) + (KK) * 128, (KK) != 0); \
    else if ((KK) < 40) wgmma_ss_n64(acc, dA + (OFF_O >> 4) + ((KK) - 36) * 2, (DW) + ((KK) - 36) * 128, 1); \
    else wgmma_rs_n64(acc, of4.x, of4.y, of4.z, of4.w, (DW) + 4 * 128, 1);                             \
  } while (0)
#define P2_RUN(T, MODE, SRC)                                                                           \
  do {                                                                                                 \
    const int hb_ = (T) & 1;                                                                           \
    const uint64_t db_ = dB64 + ((hb_ ? OFF_RING : 0) >> 4) + ((MODE) == 2 ? gridDim.z - 1 : gridDim.x - 128);       \
    const uint32_t dw_ = dB + ((OFF_WO + hb_ * 10240) >> 4);                                           \
    TURN_TAKE(41 + (T));                                                                               \
    _Pragma("unroll") for (int kk = 0; kk < 41; kk++) {                                                \
      P2_MMA(kk, db_, dw_);                                                                            \
      if (kk == ((MODE) == 2 ? P2_LW - 9 : 23) || kk == ((MODE) == 2 ? P2_LW : P2_REL) || kk == 40) wgmma_commit(); \
      if (kk == P2_LD && (MODE) != 0) {                                                                \
        _Pragma("unroll") for (int q = 0; q < 6; q++) lv[q] = ld_b128_if((SRC) + q * 256, (T) >= 3);   \
        (void)mbar_test_wait(bars + B_BIAS, 0);               \
      }                                                                                                \
      if (kk == ((MODE) == 2 ? P2_LW : P2_REL)) {                                                      \
        wgmma_wait<1>();                                                                               \
        if ((MODE) != 2) release_pair(relE + 16 * hb_, (T) < 7);                                       \
        if ((MODE) == 2) {                                                                             \
          _Pragma("unroll") for (int q = 0; q < 6; q++) lw[q] = ld_b128((SRC) + 1536 + q * 256);       \
          (void)mbar_test_wait(bars + B_BIAS, 0);                                                      \
        }                                                                                              \
      }                                                                                                \
      if (kk == P2_GIVE && !((MODE) == 2 && wg == 1)) bar_arrive(BAR_TURN0 + (wg ^ 1), 256);           \
    }                                                                                                  \
  } while (0)

    uint4 lv[6], lw[6];
    uint4* const ll0 = scr + (SC_LL + tid);
    auto ll_ptr = [&](int t) { return ll0 + (((j + t) & 7) * 2 + (t & 1)) * 1536; };
    auto ll_check = [&](uint4 (&v)[6], const uint4* src, uint32_t tag) {
#pragma unroll 1
      for (int it = 0; it < (1 << 16); it++) {
        bool ok = v[5].y == tag && v[5].z == tag;
#pragma unroll
        for (int q = 0; q < 6; q++) ok = ok && v[q].w == tag;
        if (__all_sync(0xffffffff, ok)) break;
        if (it > 1) __nanosleep(100);
#pragma unroll
        for (int q = 0; q < 6; q++) v[q] = ld_b128(src + q * 256);
      }
    };
    auto ll_add = [&](const uint4 (&v)[6]) {
#pragma unroll
      for (int q = 0; q < 5; q++) {
        acc[6 * q] += bf_lo(v[q].x); acc[6 * q + 1] += bf_hi(v[q].x);
        acc[6 * q + 2] += bf_lo(v[q].y); acc[6 * q + 3] += bf_hi(v[q].y);
        acc[6 * q + 4] += bf_lo(v[q].z); acc[6 * q + 5] += bf_hi(v[q].z);
      }
      acc[30] += bf_lo(v[5].x); acc[31] += bf_hi(v[5].x);
    };

    {
      constexpr uint32_t dw = dB + (OFF_WO >> 4);
      const uint64_t db = dB64 - 1 + gridDim.y;
      TURN_TAKE(39);
#pragma unroll
      for (int kk = 0; kk < 24; kk++) {
        P2_MMA(kk, db, dw);
        if (kk == 19) bar_arrive(BAR_TURN0 + (wg ^ 1), 256);
      }
      wgmma_commit();
      activate(2, 2); activate(2, 1); activate(2, 0);
      asm volatile("cp.async.wait_all;" ::: "memory");
#pragma unroll
      for (int i = 0; i < 4; i++) lds128(ofl + i * 2048, lv[i].x, lv[i].y, lv[i].z, lv[i].w);
      lds128(ofl - 32768, of4.x, of4.y, of4.z, of4.w);
#pragma unroll
      for (int i = 0; i < 4; i++) stsm_x4(lm_base + OFF_O + (((i * 2 + lm_x) ^ lm_sw) << 4), lv[i].x, lv[i].y, lv[i].z, lv[i].w);
      asm volatile("fence.proxy.async.shared::cta;" ::: "memory");
      wgmma_wait<0>();
      release_pair(relE, true);
      TL(40);
      TURN_TAKE(41);
#pragma unroll
      for (int kk = 24; kk < 41; kk++) {
        P2_MMA(kk, db, dw);
        if (kk == P2_GIVE) bar_arrive(BAR_TURN0 + (wg ^ 1), 256);
      }
      wgmma_commit();
      wgmma_wait<0>();
      release_pair(relE + 8, true);
      fence_regs(acc);
      uint4* pd = scr + (SC_PART + j * 1024 + warp * 128 + lane);
#pragma unroll
      for (int q = 0; q < 4; q++)
        pd[q * 32] = make_uint4(pack_bf16(acc[8 * q], acc[8 * q + 1]), pack_bf16(acc[8 * q + 2], acc[8 * q + 3]),
                                pack_bf16(acc[8 * q + 4], acc[8 * q + 5]), pack_bf16(acc[8 * q + 6], acc[8 * q + 7]));
      __syncwarp();
      if (lane == 0) mbar_arrive(bars + B_PART);
      mbar_wait(bars + B_FULL2 + 8, 0);
    }
    asm volatile("ld.shared.u32 %0, [%1];" : "=r"(tag0) : "r"(base + OFF_EPOCH) : "memory");
    tag0 = tag0 * 16u + 4u;
    auto ll_store = [&](uint4* pd, uint32_t tag) {
#pragma unroll
      for (int q = 0; q < 5; q++)
        st_b128(pd + q * 256, pack_bf16(acc[6 * q], acc[6 * q + 1]), pack_bf16(acc[6 * q + 2], acc[6 * q + 3]),
                pack_bf16(acc[6 * q + 4], acc[6 * q + 5]), tag);
      st_b128(pd + 5 * 256, pack_bf16(acc[30], acc[31]), tag, tag, tag);
    };
#pragma unroll 1
    for (int t = 1; t < 8; t++) {
      uint4* pd = ll_ptr(t);
      P2_RUN(t, 1, pd);
      if (t >= 3) {
        ll_check(lv, pd, tag0 + t - 2);
        wgmma_wait<0>();
        fence_regs(acc);
        ll_add(lv);
      } else {
        uint32_t r[4][4];
#pragma unroll
        for (int q = 0; q < 4; q++)
          ldsm_x4(r[q], t == 1 ? base + OFF_B2 + (q * 2 + lm_x) * 16 : lm_base + OFF_XT + (((q * 2 + lm_x) ^ lm_sw) << 4));
        wgmma_wait<0>();
        fence_regs(acc);
#pragma unroll
        for (int i = 0; i < 16; i++) { acc[2 * i] += bf_lo(r[i >> 2][i & 3]); acc[2 * i + 1] += bf_hi(r[i >> 2][i & 3]); }
      }
      release_pair(relE + 16 * (t & 1) + 8, t < 7);
      ll_store(pd, tag0 + t);
      mbar_wait(bars + B_FULL2 + 8 * ((t + 1) & 1), ((t + 1) >> 1) & 1);
    }
    PROF(7);
    {
      const uint4* pl = ll_ptr(8);
      P2_RUN(8, 2, pl);
      PROF(12);
      ll_check(lv, pl, tag0 + 6);
      ll_check(lw, pl + 1536, tag0 + 7);
      PROF(13);
      float sum[32];
      uint32_t z = 0;
#pragma unroll
      for (int i = 0; i < 16; i++) {
        const uint32_t a = i % 3 == 0 ? lv[i / 3].x : (i % 3 == 1 ? lv[i / 3].y : lv[i / 3].z);
        const uint32_t b = i % 3 == 0 ? lw[i / 3].x : (i % 3 == 1 ? lw[i / 3].y : lw[i / 3].z);
        sum[2 * i] = bf_lo(a) + bf_lo(b);
        sum[2 * i + 1] = bf_hi(a) + bf_hi(b);
        z ^= __float_as_uint(sum[2 * i]) ^ __float_as_uint(sum[2 * i + 1]);
      }
      PIN1(z);
      PROF(14);
      wgmma_wait<0>();
      fence_regs(acc);
#pragma unroll
      for (int i = 0; i < 32; i++) acc[i] += sum[i];
    }
    PROF(8);
#pragma unroll
    for (int q = 0; q < 4; q++)
      stsm_x4(lm_base + OFF_STG + (((q * 2 + lm_x) ^ lm_sw) << 4),
              pack_bf16(acc[8 * q], acc[8 * q + 1]), pack_bf16(acc[8 * q + 2], acc[8 * q + 3]),
              pack_bf16(acc[8 * q + 4], acc[8 * q + 5]), pack_bf16(acc[8 * q + 6], acc[8 * q + 7]));
    __syncwarp();
#pragma unroll
    for (int q = 0; q < 4; q++) {
      const int r = q * 4 + (lane >> 3);
      uint4 v;
      lds128(base + OFF_STG + (warp * 16 + r) * 128 + (((lane ^ r) & 7) << 4), v.x, v.y, v.z, v.w);
      *reinterpret_cast<uint4*>(out + (mt * 128 + (warp & 3) * 32 + 2 * r + wg) * kD + j * 64 + (lane & 7) * 8) = v;
    }
    PROF(9);
  }
}

typedef CUresult (*PFN_encodeTiled)(CUtensorMap*, CUtensorMapDataType, cuuint32_t, void*, const cuuint64_t*,
                                    const cuuint64_t*, const cuuint32_t*, const cuuint32_t*, CUtensorMapInterleave,
                                    CUtensorMapSwizzle, CUtensorMapL2promotion, CUtensorMapFloatOOBfill);

CUtensorMap make_tmap(PFN_encodeTiled fn, const void* ptr, uint64_t cols, uint64_t rows, uint32_t box_cols, uint32_t box_rows) {
  CUtensorMap m;
  cuuint64_t dims[2] = {cols, rows};
  cuuint64_t strides[1] = {cols * 2};
  cuuint32_t box[2] = {box_cols, box_rows};
  cuuint32_t es[2] = {1, 1};
  fn(&m, CU_TENSOR_MAP_DATA_TYPE_BFLOAT16, 2, const_cast<void*>(ptr), dims, strides, box, es, CU_TENSOR_MAP_INTERLEAVE_NONE,
     box_cols == 64 ? CU_TENSOR_MAP_SWIZZLE_128B : CU_TENSOR_MAP_SWIZZLE_NONE, CU_TENSOR_MAP_L2_PROMOTION_L2_128B,
     CU_TENSOR_MAP_FLOAT_OOB_FILL_NONE);
  return m;
}

}

extern "C" void kernel_launch(void* const* d_in, const int* in_sizes, int n_in, void* d_out, int out_size) {
  (void)in_sizes; (void)n_in; (void)out_size;
  const __nv_bfloat16* x = (const __nv_bfloat16*)d_in[0];
  const __nv_bfloat16* wqkv = (const __nv_bfloat16*)d_in[1];
  const __nv_bfloat16* wo = (const __nv_bfloat16*)d_in[2];
  const __nv_bfloat16* w1 = (const __nv_bfloat16*)d_in[4];
  const __nv_bfloat16* b1 = (const __nv_bfloat16*)d_in[5];
  const __nv_bfloat16* w2 = (const __nv_bfloat16*)d_in[6];
  const __nv_bfloat16* b2 = (const __nv_bfloat16*)d_in[7];
  __nv_bfloat16* out = (__nv_bfloat16*)d_out;

  static PFN_encodeTiled enc = nullptr;
  if (!enc) {
    void* p = nullptr;
    cudaDriverEntryPointQueryResult q;
    cudaGetDriverEntryPoint("cuTensorMapEncodeTiled", &p, cudaEnableDefault, &q);
    enc = (PFN_encodeTiled)p;
    cudaFuncSetAttribute(fused_kernel, cudaFuncAttributeMaxDynamicSharedMemorySize, SMEM_BYTES);
  }
  CUtensorMap tm_x = make_tmap(enc, x, 2 * kD, kS / 2, 64, 64);
  CUtensorMap tm_wqkv = make_tmap(enc, wqkv, kQKV, kD, 64, 48);
  CUtensorMap tm_wtail = make_tmap(enc, wqkv, kQKV, kD, 8, 48);
  CUtensorMap tm_w1 = make_tmap(enc, w1, kF, kD, 64, 32);
  CUtensorMap tm_w2 = make_tmap(enc, w2, kD, kF, 64, 96);
  CUtensorMap tm_wo = make_tmap(enc, wo, kD, kD, 64, 40);
  fused_kernel<<<128, 384, SMEM_BYTES, cudaStreamPerThread>>>(tm_x, tm_wqkv, tm_wtail, tm_w1, tm_w2, tm_wo, x, wqkv, wo, w1, b1, w2, b2, out);
}
```
